```python
import torch

def _softmax(x, axis=-1):
    return torch.softmax(x, dim=axis)
def _gelu(x):
    return torch.nn.functional.gelu(x, approximate="tanh")
def _silu(x):
    return torch.nn.functional.silu(x)
def _sigmoid(x):
    return torch.sigmoid(x)
def _layernorm(x, axis=-1, eps=1e-5):
    m = x.mean(dim=axis, keepdim=True)
    v = x.var(dim=axis, keepdim=True, unbiased=False)
    return (x - m) / torch.sqrt(v + eps)
def _scatter_add(tgt, idx, src, axis=0):
    return tgt.clone().index_add_(axis, idx, src)
def _segment_sum(src, seg, n):
    out = torch.zeros((n,) + src.shape[1:], dtype=src.dtype)
    return out.index_add_(0, seg, src)
def _pad(x, pw):
    flat = tuple(v for pair in reversed(pw) for v in pair)
    return torch.nn.functional.pad(x, flat)

kernel_name = 'standalone__gqa_softmax__near_ridge'

def setup_inputs():

    _w = (lambda a: (lambda t: t.to(torch.bfloat16) if t.is_floating_point() else t)(torch.as_tensor(a)))
    B, Hq, Hkv, Sq, Sk, D = 32, 32, 4, 256, 256, 128
    return {
        "q": _w((lambda *s: torch.randn(*s, dtype=torch.bfloat16) * 0.8)(B, Hq, Sq, D)),
        "k": _w((lambda *s: torch.randn(*s, dtype=torch.bfloat16) * 0.8)(B, Hkv, Sk, D)),
        "v": _w((lambda *s: torch.randn(*s, dtype=torch.bfloat16) * 0.05)(B, Hkv, Sk, D)),
    }

def reference(q, k, v):
    B, Hq, Sq, D = q.shape
    Hkv = k.shape[1]
    rep = Hq // Hkv
    k = (lambda x, n, axis: torch.repeat_interleave(x, n, dim=axis))(k, rep, axis=1)
    v = (lambda x, n, axis: torch.repeat_interleave(x, n, dim=axis))(v, rep, axis=1)
    scale = D ** -0.5
    scores = torch.einsum("bhqd,bhkd->bhqk", q, k) * scale
    p = _softmax(scores, axis=-1)
    return torch.einsum("bhqk,bhkd->bhqd", p, v)
```

```cpp
#include <cuda_runtime.h>
#include <cuda_bf16.h>
#include <cuda.h>
#include <stdint.h>

#pragma nv_diag_suppress 549

namespace {

constexpr int kNumCta      = 128;
constexpr int kTiles       = 32;
constexpr int kNumWG       = 3;
constexpr int kThreads     = kNumWG * 128;
constexpr int kTileBytes   = 64 * 128 * 2;
constexpr int kKVBytes     = 256 * 128 * 2;
constexpr int kNumQBuf     = 5;
constexpr int kVQuarter    = 5 * 4096;
constexpr int kOffK = 0;
constexpr int kOffV = kKVBytes;
constexpr int kOffQ = kOffV + 4 * kVQuarter;
constexpr int kOffBar = kOffQ + kNumQBuf * kTileBytes;
constexpr int kSmemBytes = kOffBar + 128 + 1024;

#define SM_DIST 2
#define NLATE 4
#define NPRE 6
#define PACE_W 3

static_assert(NPRE <= 8 && NLATE == 4, "the V waits below assume these match the key quarters");

struct PfTab { uint32_t e[kTiles]; };

__device__ __forceinline__ uint32_t smem_u32(const void* p) { return (uint32_t)__cvta_generic_to_shared(p); }

__device__ __forceinline__ void mbar_init(uint32_t bar, uint32_t count) {
    asm volatile("mbarrier.init.shared::cta.b64 [%0], %1;" :: "r"(bar), "r"(count) : "memory");
}
__device__ __forceinline__ void mbar_expect_tx(uint32_t bar, uint32_t bytes) {
    asm volatile("mbarrier.arrive.expect_tx.shared::cta.b64 _, [%0], %1;" :: "r"(bar), "r"(bytes) : "memory");
}
__device__ __forceinline__ bool mbar_try_wait(uint32_t bar, uint32_t parity) {
    uint32_t ok;
    asm volatile("{\n .reg .pred p;\n mbarrier.try_wait.parity.shared::cta.b64 p, [%1], %2;\n selp.u32 %0, 1, 0, p;\n}\n"
                 : "=r"(ok) : "r"(bar), "r"(parity) : "memory");
    return ok != 0;
}
__device__ __forceinline__ void mbar_wait(uint32_t bar, uint32_t parity) {
    uint32_t it = 0;
    while (!mbar_try_wait(bar, parity)) {
        if (++it > (1u << 24)) __trap();
    }
}
__device__ __forceinline__ void tma_load4d(uint32_t dst, const CUtensorMap* tm, int c3, uint32_t bar) {
    asm volatile("cp.async.bulk.tensor.4d.shared::cluster.global.mbarrier::complete_tx::bytes "
                 "[%0], [%1, {%3, %3, %3, %4}], [%2];"
                 :: "r"(dst), "l"(tm), "r"(bar), "r"(0), "r"(c3) : "memory");
}
__device__ __forceinline__ void tma_load3d(uint32_t dst, const CUtensorMap* tm, int c1, uint32_t bar) {
    asm volatile("cp.async.bulk.tensor.3d.shared::cluster.global.mbarrier::complete_tx::bytes "
                 "[%0], [%1, {%3, %4, %3}], [%2];"
                 :: "r"(dst), "l"(tm), "r"(bar), "r"(0), "r"(c1) : "memory");
}
__device__ __forceinline__ void tma_store4d(const CUtensorMap* tm, int c3, uint32_t src) {
    asm volatile("cp.async.bulk.tensor.4d.global.shared::cta.bulk_group [%0, {%2, %2, %2, %3}], [%1];"
                 :: "l"(tm), "r"(src), "r"(0), "r"(c3) : "memory");
}
template <int BYTES> __device__ __forceinline__ void l2_prefetch(const void* p) {
    asm volatile("cp.async.bulk.prefetch.L2.global [%0], %1;" :: "l"(p), "n"(BYTES) : "memory");
}
__device__ __forceinline__ bool elect_one() {
    uint32_t p;
    asm volatile("{\n .reg .pred p;\n elect.sync _|p, 0xffffffff;\n selp.u32 %0, 1, 0, p;\n}\n" : "=r"(p));
    return p != 0;
}
__device__ __forceinline__ void wg_fence()  { asm volatile("wgmma.fence.sync.aligned;" ::: "memory"); }
__device__ __forceinline__ void wg_commit() { asm volatile("wgmma.commit_group.sync.aligned;" ::: "memory"); }
template <int N> __device__ __forceinline__ void wg_wait() { asm volatile("wgmma.wait_group.sync.aligned %0;" :: "n"(N) : "memory"); }
template <int N> __device__ __forceinline__ void fence_regs(float (&d)[N]) {
#pragma unroll
    for (int i = 0; i < N; i++) asm volatile("" : "+f"(d[i]) :: "memory");
}
__device__ __forceinline__ float ex2(float x) { float y; asm("ex2.approx.ftz.f32 %0, %1;" : "=f"(y) : "f"(x)); return y; }
__device__ __forceinline__ float rcp(float x) { float y; asm("rcp.approx.ftz.f32 %0, %1;" : "=f"(y) : "f"(x)); return y; }
__device__ __forceinline__ uint32_t pack_bf16(float lo, float hi) {
    uint32_t r; asm("cvt.rn.bf16x2.f32 %0, %1, %2;" : "=r"(r) : "f"(hi), "f"(lo)); return r;
}
__device__ __forceinline__ void stmatrix_x4(uint32_t addr, uint32_t r0, uint32_t r1, uint32_t r2, uint32_t r3) {
    asm volatile("stmatrix.sync.aligned.m8n8.x4.shared.b16 [%0], {%1, %2, %3, %4};"
                 :: "r"(addr), "r"(r0), "r"(r1), "r"(r2), "r"(r3) : "memory");
}
__device__ __forceinline__ uint64_t make_desc(uint32_t addr, uint32_t lbo, uint32_t sbo, uint64_t swz) {
    return (uint64_t)((addr & 0x3FFFF) >> 4) | ((uint64_t)(lbo >> 4) << 16) | ((uint64_t)(sbo >> 4) << 32) | (swz << 62);
}
__device__ __forceinline__ void bar_arrive(int id) { asm volatile("bar.arrive %0, 256;" :: "r"(id) : "memory"); }
template <int OFF> __device__ __forceinline__ void bar_sync_off(int wg) {
    asm volatile("{\n .reg .u32 t;\n add.u32 t, %0, %1;\n bar.sync t, 256;\n}\n" :: "r"(wg), "n"(OFF) : "memory");
}

__device__ __forceinline__ void wgmma_ss_n256_first(float (&d)[128], uint64_t da, uint64_t db) {
    asm volatile(
        "wgmma.mma_async.sync.aligned.m64n256k16.f32.bf16.bf16 {"
        "%0, %1, %2, %3, %4, %5, %6, %7, %8, %9, %10, %11, %12, %13, %14, %15, "
        "%16, %17, %18, %19, %20, %21, %22, %23, %24, %25, %26, %27, %28, %29, %30, %31, "
        "%32, %33, %34, %35, %36, %37, %38, %39, %40, %41, %42, %43, %44, %45, %46, %47, "
        "%48, %49, %50, %51, %52, %53, %54, %55, %56, %57, %58, %59, %60, %61, %62, %63, "
        "%64, %65, %66, %67, %68, %69, %70, %71, %72, %73, %74, %75, %76, %77, %78, %79, "
        "%80, %81, %82, %83, %84, %85, %86, %87, %88, %89, %90, %91, %92, %93, %94, %95, "
        "%96, %97, %98, %99, %100, %101, %102, %103, %104, %105, %106, %107, %108, %109, %110, %111, "
        "%112, %113, %114, %115, %116, %117, %118, %119, %120, %121, %122, %123, %124, %125, %126, %127}, "
        "%128, %129, 0, 1, 1, 0, 0;\n"
        :
        "=f"(d[0]), "=f"(d[1]), "=f"(d[2]), "=f"(d[3]), "=f"(d[4]), "=f"(d[5]), "=f"(d[6]), "=f"(d[7]),
        "=f"(d[8]), "=f"(d[9]), "=f"(d[10]), "=f"(d[11]), "=f"(d[12]), "=f"(d[13]), "=f"(d[14]), "=f"(d[15]),
        "=f"(d[16]), "=f"(d[17]), "=f"(d[18]), "=f"(d[19]), "=f"(d[20]), "=f"(d[21]), "=f"(d[22]), "=f"(d[23]),
        "=f"(d[24]), "=f"(d[25]), "=f"(d[26]), "=f"(d[27]), "=f"(d[28]), "=f"(d[29]), "=f"(d[30]), "=f"(d[31]),
        "=f"(d[32]), "=f"(d[33]), "=f"(d[34]), "=f"(d[35]), "=f"(d[36]), "=f"(d[37]), "=f"(d[38]), "=f"(d[39]),
        "=f"(d[40]), "=f"(d[41]), "=f"(d[42]), "=f"(d[43]), "=f"(d[44]), "=f"(d[45]), "=f"(d[46]), "=f"(d[47]),
        "=f"(d[48]), "=f"(d[49]), "=f"(d[50]), "=f"(d[51]), "=f"(d[52]), "=f"(d[53]), "=f"(d[54]), "=f"(d[55]),
        "=f"(d[56]), "=f"(d[57]), "=f"(d[58]), "=f"(d[59]), "=f"(d[60]), "=f"(d[61]), "=f"(d[62]), "=f"(d[63]),
        "=f"(d[64]), "=f"(d[65]), "=f"(d[66]), "=f"(d[67]), "=f"(d[68]), "=f"(d[69]), "=f"(d[70]), "=f"(d[71]),
        "=f"(d[72]), "=f"(d[73]), "=f"(d[74]), "=f"(d[75]), "=f"(d[76]), "=f"(d[77]), "=f"(d[78]), "=f"(d[79]),
        "=f"(d[80]), "=f"(d[81]), "=f"(d[82]), "=f"(d[83]), "=f"(d[84]), "=f"(d[85]), "=f"(d[86]), "=f"(d[87]),
        "=f"(d[88]), "=f"(d[89]), "=f"(d[90]), "=f"(d[91]), "=f"(d[92]), "=f"(d[93]), "=f"(d[94]), "=f"(d[95]),
        "=f"(d[96]), "=f"(d[97]), "=f"(d[98]), "=f"(d[99]), "=f"(d[100]), "=f"(d[101]), "=f"(d[102]), "=f"(d[103]),
        "=f"(d[104]), "=f"(d[105]), "=f"(d[106]), "=f"(d[107]), "=f"(d[108]), "=f"(d[109]), "=f"(d[110]), "=f"(d[111]),
        "=f"(d[112]), "=f"(d[113]), "=f"(d[114]), "=f"(d[115]), "=f"(d[116]), "=f"(d[117]), "=f"(d[118]), "=f"(d[119]),
        "=f"(d[120]), "=f"(d[121]), "=f"(d[122]), "=f"(d[123]), "=f"(d[124]), "=f"(d[125]), "=f"(d[126]), "=f"(d[127])
        : "l"(da), "l"(db));
}
__device__ __forceinline__ void wgmma_ss_n256_acc(float (&d)[128], uint64_t da, uint64_t db) {
    asm volatile(
        "wgmma.mma_async.sync.aligned.m64n256k16.f32.bf16.bf16 {"
        "%0, %1, %2, %3, %4, %5, %6, %7, %8, %9, %10, %11, %12, %13, %14, %15, "
        "%16, %17, %18, %19, %20, %21, %22, %23, %24, %25, %26, %27, %28, %29, %30, %31, "
        "%32, %33, %34, %35, %36, %37, %38, %39, %40, %41, %42, %43, %44, %45, %46, %47, "
        "%48, %49, %50, %51, %52, %53, %54, %55, %56, %57, %58, %59, %60, %61, %62, %63, "
        "%64, %65, %66, %67, %68, %69, %70, %71, %72, %73, %74, %75, %76, %77, %78, %79, "
        "%80, %81, %82, %83, %84, %85, %86, %87, %88, %89, %90, %91, %92, %93, %94, %95, "
        "%96, %97, %98, %99, %100, %101, %102, %103, %104, %105, %106, %107, %108, %109, %110, %111, "
        "%112, %113, %114, %115, %116, %117, %118, %119, %120, %121, %122, %123, %124, %125, %126, %127}, "
        "%128, %129, 1, 1, 1, 0, 0;\n"
        :
        "+f"(d[0]), "+f"(d[1]), "+f"(d[2]), "+f"(d[3]), "+f"(d[4]), "+f"(d[5]), "+f"(d[6]), "+f"(d[7]),
        "+f"(d[8]), "+f"(d[9]), "+f"(d[10]), "+f"(d[11]), "+f"(d[12]), "+f"(d[13]), "+f"(d[14]), "+f"(d[15]),
        "+f"(d[16]), "+f"(d[17]), "+f"(d[18]), "+f"(d[19]), "+f"(d[20]), "+f"(d[21]), "+f"(d[22]), "+f"(d[23]),
        "+f"(d[24]), "+f"(d[25]), "+f"(d[26]), "+f"(d[27]), "+f"(d[28]), "+f"(d[29]), "+f"(d[30]), "+f"(d[31]),
        "+f"(d[32]), "+f"(d[33]), "+f"(d[34]), "+f"(d[35]), "+f"(d[36]), "+f"(d[37]), "+f"(d[38]), "+f"(d[39]),
        "+f"(d[40]), "+f"(d[41]), "+f"(d[42]), "+f"(d[43]), "+f"(d[44]), "+f"(d[45]), "+f"(d[46]), "+f"(d[47]),
        "+f"(d[48]), "+f"(d[49]), "+f"(d[50]), "+f"(d[51]), "+f"(d[52]), "+f"(d[53]), "+f"(d[54]), "+f"(d[55]),
        "+f"(d[56]), "+f"(d[57]), "+f"(d[58]), "+f"(d[59]), "+f"(d[60]), "+f"(d[61]), "+f"(d[62]), "+f"(d[63]),
        "+f"(d[64]), "+f"(d[65]), "+f"(d[66]), "+f"(d[67]), "+f"(d[68]), "+f"(d[69]), "+f"(d[70]), "+f"(d[71]),
        "+f"(d[72]), "+f"(d[73]), "+f"(d[74]), "+f"(d[75]), "+f"(d[76]), "+f"(d[77]), "+f"(d[78]), "+f"(d[79]),
        "+f"(d[80]), "+f"(d[81]), "+f"(d[82]), "+f"(d[83]), "+f"(d[84]), "+f"(d[85]), "+f"(d[86]), "+f"(d[87]),
        "+f"(d[88]), "+f"(d[89]), "+f"(d[90]), "+f"(d[91]), "+f"(d[92]), "+f"(d[93]), "+f"(d[94]), "+f"(d[95]),
        "+f"(d[96]), "+f"(d[97]), "+f"(d[98]), "+f"(d[99]), "+f"(d[100]), "+f"(d[101]), "+f"(d[102]), "+f"(d[103]),
        "+f"(d[104]), "+f"(d[105]), "+f"(d[106]), "+f"(d[107]), "+f"(d[108]), "+f"(d[109]), "+f"(d[110]), "+f"(d[111]),
        "+f"(d[112]), "+f"(d[113]), "+f"(d[114]), "+f"(d[115]), "+f"(d[116]), "+f"(d[117]), "+f"(d[118]), "+f"(d[119]),
        "+f"(d[120]), "+f"(d[121]), "+f"(d[122]), "+f"(d[123]), "+f"(d[124]), "+f"(d[125]), "+f"(d[126]), "+f"(d[127])
        : "l"(da), "l"(db));
}
__device__ __forceinline__ void wgmma_rs_n136_first(float (&d)[68], uint32_t a0, uint32_t a1, uint32_t a2, uint32_t a3, uint64_t db) {
    asm volatile(
        "wgmma.mma_async.sync.aligned.m64n136k16.f32.bf16.bf16 {"
        "%0, %1, %2, %3, %4, %5, %6, %7, %8, %9, %10, %11, %12, %13, %14, %15, "
        "%16, %17, %18, %19, %20, %21, %22, %23, %24, %25, %26, %27, %28, %29, %30, %31, "
        "%32, %33, %34, %35, %36, %37, %38, %39, %40, %41, %42, %43, %44, %45, %46, %47, "
        "%48, %49, %50, %51, %52, %53, %54, %55, %56, %57, %58, %59, %60, %61, %62, %63, "
        "%64, %65, %66, %67}, "
        "{%68, %69, %70, %71}, %72, 0, 1, 1, 1;\n"
        :
        "=f"(d[0]), "=f"(d[1]), "=f"(d[2]), "=f"(d[3]), "=f"(d[4]), "=f"(d[5]), "=f"(d[6]), "=f"(d[7]),
        "=f"(d[8]), "=f"(d[9]), "=f"(d[10]), "=f"(d[11]), "=f"(d[12]), "=f"(d[13]), "=f"(d[14]), "=f"(d[15]),
        "=f"(d[16]), "=f"(d[17]), "=f"(d[18]), "=f"(d[19]), "=f"(d[20]), "=f"(d[21]), "=f"(d[22]), "=f"(d[23]),
        "=f"(d[24]), "=f"(d[25]), "=f"(d[26]), "=f"(d[27]), "=f"(d[28]), "=f"(d[29]), "=f"(d[30]), "=f"(d[31]),
        "=f"(d[32]), "=f"(d[33]), "=f"(d[34]), "=f"(d[35]), "=f"(d[36]), "=f"(d[37]), "=f"(d[38]), "=f"(d[39]),
        "=f"(d[40]), "=f"(d[41]), "=f"(d[42]), "=f"(d[43]), "=f"(d[44]), "=f"(d[45]), "=f"(d[46]), "=f"(d[47]),
        "=f"(d[48]), "=f"(d[49]), "=f"(d[50]), "=f"(d[51]), "=f"(d[52]), "=f"(d[53]), "=f"(d[54]), "=f"(d[55]),
        "=f"(d[56]), "=f"(d[57]), "=f"(d[58]), "=f"(d[59]), "=f"(d[60]), "=f"(d[61]), "=f"(d[62]), "=f"(d[63]),
        "=f"(d[64]), "=f"(d[65]), "=f"(d[66]), "=f"(d[67])
        : "r"(a0), "r"(a1), "r"(a2), "r"(a3), "l"(db));
}
__device__ __forceinline__ void wgmma_rs_n136_acc(float (&d)[68], uint32_t a0, uint32_t a1, uint32_t a2, uint32_t a3, uint64_t db) {
    asm volatile(
        "wgmma.mma_async.sync.aligned.m64n136k16.f32.bf16.bf16 {"
        "%0, %1, %2, %3, %4, %5, %6, %7, %8, %9, %10, %11, %12, %13, %14, %15, "
        "%16, %17, %18, %19, %20, %21, %22, %23, %24, %25, %26, %27, %28, %29, %30, %31, "
        "%32, %33, %34, %35, %36, %37, %38, %39, %40, %41, %42, %43, %44, %45, %46, %47, "
        "%48, %49, %50, %51, %52, %53, %54, %55, %56, %57, %58, %59, %60, %61, %62, %63, "
        "%64, %65, %66, %67}, "
        "{%68, %69, %70, %71}, %72, 1, 1, 1, 1;\n"
        :
        "+f"(d[0]), "+f"(d[1]), "+f"(d[2]), "+f"(d[3]), "+f"(d[4]), "+f"(d[5]), "+f"(d[6]), "+f"(d[7]),
        "+f"(d[8]), "+f"(d[9]), "+f"(d[10]), "+f"(d[11]), "+f"(d[12]), "+f"(d[13]), "+f"(d[14]), "+f"(d[15]),
        "+f"(d[16]), "+f"(d[17]), "+f"(d[18]), "+f"(d[19]), "+f"(d[20]), "+f"(d[21]), "+f"(d[22]), "+f"(d[23]),
        "+f"(d[24]), "+f"(d[25]), "+f"(d[26]), "+f"(d[27]), "+f"(d[28]), "+f"(d[29]), "+f"(d[30]), "+f"(d[31]),
        "+f"(d[32]), "+f"(d[33]), "+f"(d[34]), "+f"(d[35]), "+f"(d[36]), "+f"(d[37]), "+f"(d[38]), "+f"(d[39]),
        "+f"(d[40]), "+f"(d[41]), "+f"(d[42]), "+f"(d[43]), "+f"(d[44]), "+f"(d[45]), "+f"(d[46]), "+f"(d[47]),
        "+f"(d[48]), "+f"(d[49]), "+f"(d[50]), "+f"(d[51]), "+f"(d[52]), "+f"(d[53]), "+f"(d[54]), "+f"(d[55]),
        "+f"(d[56]), "+f"(d[57]), "+f"(d[58]), "+f"(d[59]), "+f"(d[60]), "+f"(d[61]), "+f"(d[62]), "+f"(d[63]),
        "+f"(d[64]), "+f"(d[65]), "+f"(d[66]), "+f"(d[67])
        : "r"(a0), "r"(a1), "r"(a2), "r"(a3), "l"(db));
}

__global__ void __launch_bounds__(kThreads, 1)
gqa_kernel(const __grid_constant__ CUtensorMap tmQ, const __grid_constant__ CUtensorMap tmK,
           const __grid_constant__ CUtensorMap tmV, const __grid_constant__ CUtensorMap tmO,
           const uint32_t zero, const uint8_t* __restrict__ gq, const __grid_constant__ PfTab pft) {
    extern __shared__ uint8_t smem_raw[];
    const uint32_t sbase = (smem_u32(smem_raw) + 1023u) & ~1023u;
    const uint32_t sK = sbase + kOffK, sV = sbase + kOffV, sQ = sbase + kOffQ, sBar = sbase + kOffBar;
    const uint32_t barK = sBar + 48, barV = sBar + 80;
    const int tid = threadIdx.x;
    const int wg = (int)__reduce_max_sync(0xffffffffu, (unsigned)tid >> 7);
    const int warp = (int)__reduce_max_sync(0xffffffffu, ((unsigned)tid >> 5) & 3);
    const int lane = tid & 31;
    const int cta = blockIdx.x;
    auto tile_rg = [&](int t) { return (cta * 32 + t) * 8; };

    auto load_q = [&](int t) {
#pragma unroll
        for (int w = 0; w < 4; w++) {
            mbar_expect_tx(sBar + 8 * t, 4096);
            tma_load4d(sQ + t * kTileBytes + w * 4096, &tmQ, tile_rg(t) + w * 2, sBar + 8 * t);
        }
    };
    auto startup_issue = [&](int i) {
        if (i < 4) {
            mbar_expect_tx(barK + 8 * i, kTileBytes);
            tma_load4d(sK + i * kTileBytes, &tmK, cta * 32 + i * 8, barK + 8 * i);
        } else if (i < 7) {
            load_q(i - 4);
        } else {
            mbar_expect_tx(barV + 8 * (i - 7), kTileBytes);
            tma_load3d(sV + (10 - i) * kVQuarter, &tmV, cta * 256 + (10 - i) * 64, barV + 8 * (i - 7));
        }
    };
    if (tid == 256) {
#pragma unroll
        for (int i = 0; i < kNumQBuf; i++) mbar_init(sBar + 8 * i, 4);
#pragma unroll
        for (int i = 0; i < 8; i++) mbar_init(barK + 8 * i, 1);
        asm volatile("fence.mbarrier_init.release.cluster;" ::: "memory");
        asm volatile("fence.proxy.async.shared::cta;" ::: "memory");
#pragma unroll
        for (int i = 0; i < PACE_W; i++) startup_issue(i);
    }
    if (tid < 256) {
#pragma unroll
        for (int i = 0; i < 4; i++)
            asm volatile("st.shared.v4.b32 [%0], {%1, %1, %1, %1};" :: "r"(sV + i * kVQuarter + 16384 + tid * 16), "r"(0x3F803F80u) : "memory");
        asm volatile("fence.proxy.async.shared::cta;" ::: "memory");
    }
    __syncthreads();
    if (tid == 256) {
#pragma unroll
        for (int i = PACE_W; i < 11; i++) {
            const int w = i - PACE_W;
            if (w < 7) mbar_wait(w < 4 ? barK + 8 * w : sBar + 8 * (w - 4), 0);
            startup_issue(i);
        }
    }
    __syncwarp();
#pragma unroll
    for (int i = 0; i < 4; i++) mbar_wait(barK + 8 * i, 0);

    const uint64_t descK = make_desc(sK, 16, 2048, 1);
    const uint64_t descV = make_desc(sV, 4096, 512, 2);
    const float c = 0.08838834764831845f * 1.4426950408889634f;
    const uint32_t st_row = lane & 7, st_m = lane >> 3;
    const uint32_t st_off = warp * 4096 + (st_m & 1) * 2048 + st_row * 128 + ((((st_m >> 1) ^ st_row) & 7) << 4);

    auto refill = [&](int tp, int b) {
        if (tp + kNumQBuf < kTiles) {
            asm volatile("cp.async.bulk.wait_group.read 0;" ::: "memory");
            mbar_expect_tx(sBar + 8 * b, 4096);
            tma_load4d(sQ + b * kTileBytes + warp * 4096, &tmQ, tile_rg(tp + kNumQBuf) + warp * 2, sBar + 8 * b);
        }
        const uint32_t e = pft.e[tp];
        if (e & 255) l2_prefetch<4096>(gq + (size_t)(uint32_t)(tile_rg(e & 255) + warp * 2) * 2048);
        if (e & 0xff00) l2_prefetch<4096>(gq + (size_t)(uint32_t)(tile_rg((e >> 8) & 255) + warp * 2) * 2048);
    };

    int n = 0;
    for (int t = wg; t < kTiles; t += kNumWG, n++) {
        const int buf = (pft.e[t] >> 24) & 7, phase = pft.e[t] >> 31;
        const uint32_t qbuf = sQ + buf * kTileBytes;
        mbar_wait(sBar + 8 * buf, phase);
        float s[128];
        const uint64_t descQ = make_desc(qbuf, 16, 2048, 1);
        if (t != 0) bar_sync_off<1>(wg);
        wg_fence();
        wgmma_ss_n256_first(s, descQ, descK);
#pragma unroll
        for (int kk = 1; kk < 8; kk++) {
            const uint64_t off = (uint64_t)(((kk >> 2) * 1024 + (kk & 3) * 32) >> 4);
            wgmma_ss_n256_acc(s, descQ + off, descK + off);
        }
        wg_commit();
        bar_arrive((pft.e[t] >> 16) & 15);
        if (n == 1) {
            asm volatile("cp.async.bulk.wait_group.read 0;" ::: "memory");
            __syncwarp();
            if (elect_one()) refill(wg, wg);
            __syncwarp();
        }
        wg_wait<0>();
        fence_regs(s);

        float m0, m1;
        {
            int a0 = max(__float_as_int(s[0]), __float_as_int(s[1])), a1 = max(__float_as_int(s[2]), __float_as_int(s[3]));
            int b0 = max(__float_as_int(s[4]), __float_as_int(s[5])), b1 = max(__float_as_int(s[6]), __float_as_int(s[7]));
#pragma unroll
            for (int j = 8; j < 128; j += 8) {
                a0 = __vimax3_s32(a0, __float_as_int(s[j]), __float_as_int(s[j + 1]));
                a1 = __vimax3_s32(a1, __float_as_int(s[j + 2]), __float_as_int(s[j + 3]));
                b0 = __vimax3_s32(b0, __float_as_int(s[j + 4]), __float_as_int(s[j + 5]));
                b1 = __vimax3_s32(b1, __float_as_int(s[j + 6]), __float_as_int(s[j + 7]));
            }
            a0 = max(a0, b0); a1 = max(a1, b1);
            a0 = max(a0, __shfl_xor_sync(0xffffffffu, a0, 1));
            a1 = max(a1, __shfl_xor_sync(0xffffffffu, a1, 1));
            a0 = max(a0, __shfl_xor_sync(0xffffffffu, a0, 2));
            a1 = max(a1, __shfl_xor_sync(0xffffffffu, a1, 2));
            m0 = __int_as_float(a0); m1 = __int_as_float(a1);
            if (__any_sync(0xffffffffu, (a0 | a1) < 0)) {
                uint32_t u0 = min(__float_as_uint(s[0]), __float_as_uint(s[1])), u1 = min(__float_as_uint(s[2]), __float_as_uint(s[3]));
                uint32_t v0 = min(__float_as_uint(s[4]), __float_as_uint(s[5])), v1 = min(__float_as_uint(s[6]), __float_as_uint(s[7]));
#pragma unroll
                for (int j = 8; j < 128; j += 8) {
                    u0 = __vimin3_u32(u0, __float_as_uint(s[j]), __float_as_uint(s[j + 1]));
                    u1 = __vimin3_u32(u1, __float_as_uint(s[j + 2]), __float_as_uint(s[j + 3]));
                    v0 = __vimin3_u32(v0, __float_as_uint(s[j + 4]), __float_as_uint(s[j + 5]));
                    v1 = __vimin3_u32(v1, __float_as_uint(s[j + 6]), __float_as_uint(s[j + 7]));
                }
                u0 = min(u0, v0); u1 = min(u1, v1);
                u0 = min(u0, __shfl_xor_sync(0xffffffffu, u0, 1));
                u1 = min(u1, __shfl_xor_sync(0xffffffffu, u1, 1));
                u0 = min(u0, __shfl_xor_sync(0xffffffffu, u0, 2));
                u1 = min(u1, __shfl_xor_sync(0xffffffffu, u1, 2));
                if (a0 < 0) m0 = __uint_as_float(u0);
                if (a1 < 0) m1 = __uint_as_float(u1);
            }
        }
        const float nm0 = -m0 * c, nm1 = -m1 * c;
        uint32_t p[64];
        auto scale_chunk = [&](const int k) {
            const int kd = k + SM_DIST;
            float a0 = nm0, a1 = nm1;
            if (kd < 16 && kd >= NLATE) {
                a0 = __uint_as_float(__float_as_uint(nm0) ^ (p[4 * kd + 2] & zero));
                a1 = __uint_as_float(__float_as_uint(nm1) ^ (p[4 * kd + 3] & zero));
            }
#pragma unroll
            for (int e = 0; e < 8; e++) s[8 * k + e] = fmaf(s[8 * k + e], c, (e & 2) ? a1 : a0);
        };
        auto exp_chunk = [&](const int k) {
#pragma unroll
            for (int e = 0; e < 4; e++) p[4 * k + e] = pack_bf16(ex2(s[8 * k + 2 * e]), ex2(s[8 * k + 2 * e + 1]));
        };
        auto vdesc = [&](int kk) { return descV + (uint64_t)(((kk >> 2) * kVQuarter + (kk & 3) * 1024) >> 4); };
#pragma unroll
        for (int k = 15; k >= NLATE; k--) { scale_chunk(k); exp_chunk(k); }
#pragma unroll
        for (int k = NLATE - 1; k >= 0; k--) scale_chunk(k);

        if (n == 0) {
#pragma unroll
            for (int i = 0; i < 2; i++) mbar_wait(barV + 8 * i, 0);
        }
        float o[68];
        bar_sync_off<4>(wg);
        wg_fence();
        wgmma_rs_n136_first(o, p[60], p[61], p[62], p[63], vdesc(15));
#pragma unroll
        for (int kk = 14; kk >= NLATE; kk--) {
            wgmma_rs_n136_acc(o, p[4 * kk], p[4 * kk + 1], p[4 * kk + 2], p[4 * kk + 3], vdesc(kk));
            if (kk == 16 - NPRE && n == 0) {
                if (t == 0) bar_arrive((pft.e[0] >> 20) & 15);
                mbar_wait(barV + 16, 0);
                if (wg + warp == 0 && elect_one()) load_q(3);
                __syncwarp();
            }
        }
#pragma unroll
        for (int k = NLATE - 1; k >= 0; k--) exp_chunk(k);
        if (n == 0) {
            mbar_wait(barV + 24, 0);
            if (wg == 1 && warp == 0 && elect_one()) load_q(4);
            __syncwarp();
        }
        wg_fence();
#pragma unroll
        for (int kk = NLATE - 1; kk >= 0; kk--)
            wgmma_rs_n136_acc(o, p[4 * kk], p[4 * kk + 1], p[4 * kk + 2], p[4 * kk + 3], vdesc(kk));
        wg_commit();
        if (t != kTiles - 1 && t != 0) bar_arrive((pft.e[t] >> 20) & 15);
        wg_wait<0>();
        fence_regs(o);

        const float r0 = rcp(o[64]), r1 = rcp(o[66]);
        const uint32_t st_base = qbuf + st_off;
#pragma unroll
        for (int j = 0; j < 16; j += 2) {
            stmatrix_x4((st_base ^ ((j & 7) << 4)) + (j >> 3) * 1024,
                        pack_bf16(o[4 * j] * r0, o[4 * j + 1] * r0),
                        pack_bf16(o[4 * j + 2] * r1, o[4 * j + 3] * r1),
                        pack_bf16(o[4 * j + 4] * r0, o[4 * j + 5] * r0),
                        pack_bf16(o[4 * j + 6] * r1, o[4 * j + 7] * r1));
        }
        asm volatile("fence.proxy.async.shared::cta;" ::: "memory");
        __syncwarp();
        if (elect_one()) {
            tma_store4d(&tmO, tile_rg(t) + warp * 2, qbuf + warp * 4096);
            asm volatile("cp.async.bulk.commit_group;" ::: "memory");
            if (n != 0) refill(t, buf);
        }
        __syncwarp();
    }
    asm volatile("cp.async.bulk.wait_group.read 0;" ::: "memory");
}

typedef CUresult (*EncodeFn)(CUtensorMap*, CUtensorMapDataType, cuuint32_t, void*, const cuuint64_t*, const cuuint64_t*,
                             const cuuint32_t*, const cuuint32_t*, CUtensorMapInterleave, CUtensorMapSwizzle,
                             CUtensorMapL2promotion, CUtensorMapFloatOOBfill);

void make_map(EncodeFn fn, CUtensorMap* m, const void* ptr, uint64_t rows, uint32_t groups) {
    cuuint64_t dims[4] = {64, 8, 2, rows / 8};
    cuuint64_t strides[3] = {256, 128, 2048};
    cuuint32_t box[4] = {64, 8, 2, groups};
    cuuint32_t es[4] = {1, 1, 1, 1};
    fn(m, CU_TENSOR_MAP_DATA_TYPE_BFLOAT16, 4, const_cast<void*>(ptr), dims, strides, box, es,
       CU_TENSOR_MAP_INTERLEAVE_NONE, CU_TENSOR_MAP_SWIZZLE_128B, CU_TENSOR_MAP_L2_PROMOTION_L2_256B,
       CU_TENSOR_MAP_FLOAT_OOB_FILL_NONE);
}
void make_map_v(EncodeFn fn, CUtensorMap* m, const void* ptr, uint64_t rows) {
    cuuint64_t dims[3] = {32, rows, 4};
    cuuint64_t strides[2] = {256, 64};
    cuuint32_t box[3] = {32, 64, 4};
    cuuint32_t es[3] = {1, 1, 1};
    fn(m, CU_TENSOR_MAP_DATA_TYPE_BFLOAT16, 3, const_cast<void*>(ptr), dims, strides, box, es,
       CU_TENSOR_MAP_INTERLEAVE_NONE, CU_TENSOR_MAP_SWIZZLE_64B, CU_TENSOR_MAP_L2_PROMOTION_L2_256B,
       CU_TENSOR_MAP_FLOAT_OOB_FILL_NONE);
}

#define PF_MAX 3
#define PF_END 18
#define PF_STEP 3
#define PF_START 2
int pf_lead(int t) {
    if (t < 0) return 1;
    const int up = t + 1 - (PF_START), dn = (PF_END) - t >= 0 ? ((PF_END) - t) / (PF_STEP) + 1 : 0;
    int l = up < dn ? up : dn;
    l = l < (PF_MAX) ? l : (PF_MAX);
    return l > 1 ? l : 1;
}

}

extern "C" void kernel_launch(void* const* d_in, const int* in_sizes, int n_in, void* d_out, int out_size) {
    (void)in_sizes; (void)n_in; (void)out_size;
    static EncodeFn fn = nullptr;
    if (!fn) {
        void* p = nullptr;
        cudaDriverEntryPointQueryResult qr;
        cudaGetDriverEntryPoint("cuTensorMapEncodeTiled", &p, cudaEnableDefault, &qr);
        fn = (EncodeFn)p;
        cudaFuncSetAttribute(gqa_kernel, cudaFuncAttributeMaxDynamicSharedMemorySize, kSmemBytes);
    }
    CUtensorMap tmQ, tmK, tmV, tmO;
    make_map(fn, &tmQ, d_in[0], 32ull * 32 * 256, 2);
    make_map(fn, &tmK, d_in[1], 32ull * 4 * 256, 8);
    make_map_v(fn, &tmV, d_in[2], 32ull * 4 * 256);
    make_map(fn, &tmO, d_out, 32ull * 32 * 256, 2);
    PfTab pft;
    for (int t = 0; t < kTiles; t++) {
        const int lo = t + kNumQBuf + pf_lead(t - 1);
        int hi = t + kNumQBuf + pf_lead(t);
        if (hi > kTiles - 1) hi = kTiles - 1;
        pft.e[t] = (lo <= hi ? lo : 0) | (lo + 1 <= hi ? (lo + 1) << 8 : 0) |
                   (uint32_t)(t % kNumQBuf) << 24 | (uint32_t)((t / kNumQBuf) & 1) << 31;
    }
    {
        int ord[2 * kTiles], len = 0, nq = 0, np = 0;
        while (nq < 3) ord[len++] = 2 * nq++;
        while (np < 2) ord[len++] = 2 * np++ + 1;
        while (nq < kTiles - 2) { ord[len++] = 2 * nq++; ord[len++] = 2 * np++ + 1; }
        while (nq < kTiles) ord[len++] = 2 * nq++;
        while (np < kTiles) ord[len++] = 2 * np++ + 1;
        for (int i = 0; i + 1 < len; i++) {
            const uint32_t id = ((ord[i + 1] & 1) ? 4 : 1) + (ord[i + 1] >> 1) % kNumWG;
            pft.e[ord[i] >> 1] |= id << ((ord[i] & 1) ? 20 : 16);
        }
    }
    gqa_kernel<<<kNumCta, kThreads, kSmemBytes>>>(tmQ, tmK, tmV, tmO, 0u, (const uint8_t*)d_in[0], pft);
}
```
